```python
import torch

def _softmax(x, axis=-1):
    return torch.softmax(x, dim=axis)
def _gelu(x):
    return torch.nn.functional.gelu(x, approximate="tanh")
def _silu(x):
    return torch.nn.functional.silu(x)
def _sigmoid(x):
    return torch.sigmoid(x)
def _layernorm(x, axis=-1, eps=1e-5):
    m = x.mean(dim=axis, keepdim=True)
    v = x.var(dim=axis, keepdim=True, unbiased=False)
    return (x - m) / torch.sqrt(v + eps)
def _scatter_add(tgt, idx, src, axis=0):
    return tgt.clone().index_add_(axis, idx, src)
def _segment_sum(src, seg, n):
    out = torch.zeros((n,) + src.shape[1:], dtype=src.dtype)
    return out.index_add_(0, seg, src)
def _pad(x, pw):
    flat = tuple(v for pair in reversed(pw) for v in pair)
    return torch.nn.functional.pad(x, flat)

kernel_name = 'sequential_preLN__spectral_gfnet__mixer_token_mlp__prompt'

def setup_inputs():

    _w = (lambda a: (lambda t: t.to(torch.bfloat16) if t.is_floating_point() else t)(torch.as_tensor(a)))
    def _A_setup():
        B, S, D = 1, 2048, 512
        Df = D // 2 + 1
        return {
            "x": _w((lambda *s: torch.randn(*s, dtype=torch.bfloat16) * 0.05)(B, S, D)),
            "w_r": _w((lambda *s: torch.randn(*s, dtype=torch.bfloat16) * 0.2)(S, Df) * 0.02),
            "w_i": _w((lambda *s: torch.randn(*s, dtype=torch.bfloat16) * 0.2)(S, Df) * 0.02),
        }
    _A_in = _A_setup()

    def _B_setup():
        B, S, D, F = 1, 2048, 512, 1376
        return {
            "x": _w((lambda *s: torch.randn(*s, dtype=torch.bfloat16) * 0.05)(B, S, D)),
            "w1": _w((lambda *s: torch.randn(*s, dtype=torch.bfloat16) * 0.4)(S, F) * (S ** -0.5)),
            "b1": _w((lambda *s: torch.randn(*s, dtype=torch.bfloat16) * 3.2)(F) * 0.02),
            "w2": _w((lambda *s: torch.randn(*s, dtype=torch.bfloat16) * 0.2)(F, S) * (F ** -0.5)),
            "b2": _w((lambda *s: torch.randn(*s, dtype=torch.bfloat16) * 0.4)(S) * 0.02),
        }
    _B_in = _B_setup()

    return {
        "A_x": _A_in["x"],
        "A_w_r": _A_in["w_r"],
        "A_w_i": _A_in["w_i"],
        "B_x": _B_in["x"],
        "B_w1": _B_in["w1"],
        "B_b1": _B_in["b1"],
        "B_w2": _B_in["w2"],
        "B_b2": _B_in["b2"],
    }

def reference(A_x, A_w_r, A_w_i, B_x, B_w1, B_b1, B_w2, B_b2):
    def _A_ref(x, w_r, w_i):
        B, S, D = x.shape
        X = (lambda x, axes=(-2,-1): torch.fft.rfft2(x.float(), dim=axes))(x, axes=(-2, -1))
        W = w_r + 1j * w_i
        X = X * W
        y = (lambda x, s, axes=(-2,-1): torch.fft.irfft2(x, s=s, dim=axes).to(torch.bfloat16))(X, (S, D), axes=(-2, -1))
        return y

    def _B_ref(x, w1, b1, w2, b2):
        B, S, D = x.shape
        h = _layernorm(x, axis=-1)
        u = torch.einsum("bsd,sf->bdf", h, w1) + b1
        u = _gelu(u)
        y = torch.einsum("bdf,fs->bds", u, w2) + b2
        return (lambda x, *d: x.permute(*d))(y, 0, 2, 1)

    x = A_x
    h = x + _A_ref(_layernorm(x, axis=-1), A_w_r, A_w_i)
    h2 = h + _B_ref(_layernorm(h, axis=-1), B_w1, B_b1, B_w2, B_b2)
    return h2
```

```cpp
#include <cuda_runtime.h>
#include <cuda_bf16.h>
#include <cuda.h>
#include <stdint.h>

constexpr int NCTA = 128;
constexpr int NTHR = 608;
constexpr int NSLOT = 6;
constexpr int LEAD1 = 4, LEAD2 = 4;
constexpr int W1_RES = 14;
constexpr int NW0 = 0, NW1 = 3, NW2 = 2, NW3 = 1;
constexpr int W2A = 6, W2B = 8;
constexpr uint32_t GA = 600, GB = 1000, GC = 0, GAP1 = 300, GAP2 = 250;
constexpr uint32_t SM_W = 0;
constexpr uint32_t SM_RING = 180224;
constexpr uint32_t SM_WS = 147456;
constexpr uint32_t SM_WT = SM_RING;
constexpr uint32_t SM_TB = SM_RING + 18944;
constexpr uint32_t SM_XB = SM_RING + 30208;
constexpr uint32_t SM_BAR = SM_RING + NSLOT * 8192;
constexpr uint32_t SM_TOTAL = SM_BAR + 512;
constexpr uint32_t B_FULL = 0, B_EMPTY = 6, B_W1 = 12, B_W2 = 20, B_WF = 31, B_EPI = 32, B_S4 = 33, B_RFREE = 34, B_RECV = 36, B_GO = 38,
                   B_TAIL = 42, B_G1DONE = 43, B_K3 = 44, B_COUNT = 45;

__device__ uint4 g_Y[128 * 128 * 8];
__device__ uint2 g_Y128[16 * 128 * 4];
__device__ uint4 g_hn[8 * 32 * 512];
__device__ uint4 g_u[8 * 22 * 512];
__device__ float2 g_st[2048 * 4];
__device__ unsigned g_cnt[32 * 32];
#define TS(i)
#define TSX(i)
#define TS_T 0

__device__ __forceinline__ uint32_t pack2(float lo, float hi) {
    uint32_t r; asm("cvt.rn.bf16x2.f32 %0,%1,%2;" : "=r"(r) : "f"(hi), "f"(lo)); return r;
}
__device__ __forceinline__ float blo(uint32_t v) { return __uint_as_float(v << 16); }
__device__ __forceinline__ float bhi(uint32_t v) { return __uint_as_float(v & 0xffff0000u); }
__device__ __forceinline__ void mma0(float (&c)[4], uint32_t a0, uint32_t a1, uint32_t a2, uint32_t a3, uint32_t b0, uint32_t b1) {
    asm("mma.sync.aligned.m16n8k16.row.col.f32.bf16.bf16.f32 {%0,%1,%2,%3},{%4,%5,%6,%7},{%8,%9},{%10,%10,%10,%10};"
        : "=f"(c[0]), "=f"(c[1]), "=f"(c[2]), "=f"(c[3]) : "r"(a0), "r"(a1), "r"(a2), "r"(a3), "r"(b0), "r"(b1), "f"(0.f));
}
__device__ __forceinline__ void mma1(float (&c)[4], uint32_t a0, uint32_t a1, uint32_t a2, uint32_t a3, uint32_t b0, uint32_t b1) {
    asm("mma.sync.aligned.m16n8k16.row.col.f32.bf16.bf16.f32 {%0,%1,%2,%3},{%4,%5,%6,%7},{%8,%9},{%0,%1,%2,%3};"
        : "+f"(c[0]), "+f"(c[1]), "+f"(c[2]), "+f"(c[3]) : "r"(a0), "r"(a1), "r"(a2), "r"(a3), "r"(b0), "r"(b1));
}
__device__ __forceinline__ uint32_t hmul(uint32_t a, uint32_t b) { uint32_t r; asm("mul.rn.bf16x2 %0,%1,%2;" : "=r"(r) : "r"(a), "r"(b)); return r; }
__device__ __forceinline__ uint32_t hfma(uint32_t a, uint32_t b, uint32_t c) { uint32_t r; asm("fma.rn.bf16x2 %0,%1,%2,%3;" : "=r"(r) : "r"(a), "r"(b), "r"(c)); return r; }
__device__ __forceinline__ uint32_t hneg(uint32_t a) { uint32_t r; asm("neg.bf16x2 %0,%1;" : "=r"(r) : "r"(a)); return r; }
__device__ __forceinline__ uint32_t htw(uint32_t v, uint32_t A, uint32_t B) {
    uint32_t r;
    asm("{.reg .b16 l,h; .reg .b32 a,b; mov.b32 {l,h},%1; mov.b32 a,{l,l}; mov.b32 b,{h,h}; mul.rn.bf16x2 a,a,%2; fma.rn.bf16x2 %0,b,%3,a;}" : "=r"(r) : "r"(v), "r"(A), "r"(B));
    return r;
}
template <bool ACC = false>
__device__ __forceinline__ void dft16(float (&re)[2][4], float (&im)[2][4], const uint4 (&C)[4], const uint2 (&d)[4]) {
    if constexpr (ACC) {
        mma1(re[0], C[0].x, C[0].y, C[0].z, C[0].w, d[0].x, d[1].x);
        mma1(im[0], C[2].x, C[2].y, C[2].z, C[2].w, d[0].x, d[1].x);
        mma1(re[1], C[0].x, C[0].y, C[0].z, C[0].w, d[0].y, d[1].y);
        mma1(im[1], C[2].x, C[2].y, C[2].z, C[2].w, d[0].y, d[1].y);
    } else {
        mma0(re[0], C[0].x, C[0].y, C[0].z, C[0].w, d[0].x, d[1].x);
        mma0(im[0], C[2].x, C[2].y, C[2].z, C[2].w, d[0].x, d[1].x);
        mma0(re[1], C[0].x, C[0].y, C[0].z, C[0].w, d[0].y, d[1].y);
        mma0(im[1], C[2].x, C[2].y, C[2].z, C[2].w, d[0].y, d[1].y);
    }
    mma1(re[0], C[1].x, C[1].y, C[1].z, C[1].w, d[2].x, d[3].x);
    mma1(im[0], C[3].x, C[3].y, C[3].z, C[3].w, d[2].x, d[3].x);
    mma1(re[1], C[1].x, C[1].y, C[1].z, C[1].w, d[2].y, d[3].y);
    mma1(im[1], C[3].x, C[3].y, C[3].z, C[3].w, d[2].y, d[3].y);
}
__device__ __forceinline__ float rowsum(uint32_t a0, uint32_t a1, uint32_t a2, uint32_t a3, uint32_t a4, uint32_t a5, uint32_t a6, uint32_t a7) {
    const uint32_t one = 0x3f803f80u;
    float c[4], e[4];
    mma0(c, one, one, one, one, a0, a1); mma0(e, one, one, one, one, a2, a3);
    mma1(c, one, one, one, one, a4, a5); mma1(e, one, one, one, one, a6, a7);
    float v = (c[0] + c[1]) + (e[0] + e[1]);
    v += __shfl_xor_sync(~0u, v, 1);
    return v + __shfl_xor_sync(~0u, v, 2);
}
__device__ __forceinline__ float sumsq(const float (&re)[2][4], const float (&im)[2][4]) {
    float a = re[0][0] * re[0][0], c = im[0][0] * im[0][0];
#pragma unroll
    for (int k = 1; k < 8; k++) { a = fmaf(re[k >> 2][k & 3], re[k >> 2][k & 3], a); c = fmaf(im[k >> 2][k & 3], im[k >> 2][k & 3], c); }
    a += c;
#pragma unroll
    for (int o = 16; o; o >>= 1) a += __shfl_xor_sync(~0u, a, o);
    return a;
}
template <int LOGN> __device__ __forceinline__ void cs(int k, float& c, float& s) {
    int kk = (k << (32 - LOGN)) >> (32 - LOGN);
    float a = (float)kk * (6.283185307179586f / (float)(1 << LOGN));
    s = __sinf(a); c = __cosf(a);
}
__device__ __forceinline__ void rowtw(const float (&re)[2][4], const float (&im)[2][4], const uint4 (&W)[4], uint2 (&d)[4]) {
#pragma unroll
    for (int tau = 0; tau < 2; tau++) {
        d[tau].x = htw(pack2(re[tau][0], im[tau][0]), W[tau].x, W[2 + tau].x);
        d[2 + tau].x = htw(pack2(re[tau][1], im[tau][1]), W[tau].y, W[2 + tau].y);
        d[tau].y = htw(pack2(re[tau][2], im[tau][2]), W[tau].z, W[2 + tau].z);
        d[2 + tau].y = htw(pack2(re[tau][3], im[tau][3]), W[tau].w, W[2 + tau].w);
    }
}
__device__ __forceinline__ uint2 ldv64(const void* p) { uint2 v; asm volatile("ld.relaxed.gpu.global.v2.u32 {%0,%1},[%2];" : "=r"(v.x), "=r"(v.y) : "l"(p) : "memory"); return v; }
__device__ __forceinline__ uint4 ldv128(const void* p) { uint4 v; asm volatile("ld.relaxed.gpu.global.v4.u32 {%0,%1,%2,%3},[%4];" : "=r"(v.x), "=r"(v.y), "=r"(v.z), "=r"(v.w) : "l"(p) : "memory"); return v; }
__device__ __forceinline__ void mbar_init(uint32_t a, uint32_t n) { asm volatile("mbarrier.init.shared.b64 [%0],%1;" ::"r"(a), "r"(n) : "memory"); }
__device__ __forceinline__ void mbar_expect(uint32_t a, uint32_t bytes) { asm volatile("mbarrier.arrive.expect_tx.shared.b64 _,[%0],%1;" ::"r"(a), "r"(bytes) : "memory"); }
__device__ __forceinline__ void mbar_arrive(uint32_t a) { asm volatile("mbarrier.arrive.shared.b64 _,[%0];" ::"r"(a) : "memory"); }
__device__ __forceinline__ uint32_t mbar_try(uint32_t a, uint32_t parity) {
    uint32_t ok;
    asm volatile("{.reg .pred p; mbarrier.try_wait.parity.shared.b64 p,[%1],%2; selp.u32 %0,1,0,p;}" : "=r"(ok) : "r"(a), "r"(parity) : "memory");
    return ok;
}
__device__ __forceinline__ uint32_t mbar_test(uint32_t a, uint32_t parity) {
    uint32_t ok;
    asm volatile("{.reg .pred p; mbarrier.test_wait.parity.shared.b64 p,[%1],%2; selp.u32 %0,1,0,p;}" : "=r"(ok) : "r"(a), "r"(parity) : "memory");
    return ok;
}
__device__ __forceinline__ void mbar_wait(uint32_t a, uint32_t parity) {
    int it = 0;
    while (!mbar_try(a, parity) && ++it < (1 << 20)) {}
}
__device__ __forceinline__ void mbar_wait_cluster(uint32_t a, uint32_t parity) {
    uint32_t ok; int it = 0;
    do {
        asm volatile("{.reg .pred p; mbarrier.try_wait.parity.acquire.cluster.shared::cta.b64 p,[%1],%2; selp.u32 %0,1,0,p;}" : "=r"(ok) : "r"(a), "r"(parity) : "memory");
    } while (!ok && ++it < (1 << 20));
}
__device__ __forceinline__ void bulk_load(uint32_t dst, const void* src, uint32_t bytes, uint32_t bar) {
    asm volatile("cp.async.bulk.shared::cluster.global.mbarrier::complete_tx::bytes [%0],[%1],%2,[%3];" ::"r"(dst), "l"(src), "r"(bytes), "r"(bar) : "memory");
}
__device__ __forceinline__ void cnt_arrive(unsigned* p) { asm volatile("red.release.gpu.global.add.u32 [%0],1;" ::"l"(p) : "memory"); }
__device__ __forceinline__ void cnt_wait(unsigned* p, unsigned target) {
    unsigned v; int it = 0;
    do { asm volatile("ld.acquire.gpu.global.u32 %0,[%1];" : "=r"(v) : "l"(p) : "memory"); } while ((int)(v - target) < 0 && ++it < (1 << 20));
}
__device__ __forceinline__ void l2_prefetch(const void* p, uint32_t n) { asm volatile("cp.async.bulk.prefetch.L2.global [%0],%1;" ::"l"(p), "r"(n) : "memory"); }
__device__ __forceinline__ void pause(uint32_t n) {
    const uint32_t t0 = clock();
    for (int it = 0; n && (uint32_t)clock() - t0 < n && it < 4096; it++) {}
}
__device__ __forceinline__ void paced_prefetch(const char* p, uint32_t gap) {
    uint32_t t0 = clock();
#pragma unroll 1
    for (int i = 0; i < 8; i++) {
        l2_prefetch(p + i * 5504, 5504);
        for (int it = 0; i < 7 && (uint32_t)clock() - t0 < gap && it < 4096; it++) {}
        t0 += gap;
    }
}
__device__ __forceinline__ void fence_async() { asm volatile("fence.proxy.async.global;" ::: "memory"); }
#define BAR_SYNC(id, n) asm volatile("bar.sync " #id "," #n ";" ::: "memory")
#define BAR_ARRIVE(id, n) asm volatile("bar.arrive " #id "," #n ";" ::: "memory")
__device__ __forceinline__ uint64_t mkdesc(uint32_t addr, uint32_t lbo, uint32_t sbo, int sw) {
    return (uint64_t)((addr & 0x3FFFF) >> 4) | ((uint64_t)(lbo >> 4) << 16) | ((uint64_t)(sbo >> 4) << 32) | ((uint64_t)sw << 62);
}
__device__ __forceinline__ void sts32(uint32_t a, uint32_t v) { asm volatile("st.shared.u32 [%0],%1;" ::"r"(a), "r"(v) : "memory"); }
__device__ __forceinline__ void sts64(uint32_t a, uint32_t x, uint32_t y) { asm volatile("st.shared.v2.u32 [%0],{%1,%2};" ::"r"(a), "r"(x), "r"(y) : "memory"); }
__device__ __forceinline__ uint2 lds64(uint32_t a) { uint2 v; asm volatile("ld.shared.v2.u32 {%0,%1},[%2];" : "=r"(v.x), "=r"(v.y) : "r"(a) : "memory"); return v; }
__device__ __forceinline__ uint32_t lds32(uint32_t a) { uint32_t v; asm volatile("ld.shared.u32 %0,[%1];" : "=r"(v) : "r"(a) : "memory"); return v; }
__device__ __forceinline__ uint4 lds128(uint32_t a) { uint4 v; asm volatile("ld.shared.v4.u32 {%0,%1,%2,%3},[%4];" : "=r"(v.x), "=r"(v.y), "=r"(v.z), "=r"(v.w) : "r"(a) : "memory"); return v; }
__device__ __forceinline__ void sts128(uint32_t a, uint4 v) { asm volatile("st.shared.v4.u32 [%0],{%1,%2,%3,%4};" ::"r"(a), "r"(v.x), "r"(v.y), "r"(v.z), "r"(v.w) : "memory"); }
__device__ __forceinline__ void ldtab(uint4 (&C)[4], uint32_t a) {
#pragma unroll
    for (int q = 0; q < 4; q++) C[q] = lds128(a + q * 512);
}
__device__ __forceinline__ float lds_bf(uint32_t a) { unsigned short v; asm volatile("ld.shared.u16 %0,[%1];" : "=h"(v) : "r"(a) : "memory"); return __uint_as_float((uint32_t)v << 16); }
__device__ __forceinline__ float ldg_bf(const __nv_bfloat16* p) { return __uint_as_float((uint32_t)__ldg((const unsigned short*)p) << 16); }
__device__ __forceinline__ void wg_fence() { asm volatile("wgmma.fence.sync.aligned;" ::: "memory"); }
__device__ __forceinline__ void wg_commit() { asm volatile("wgmma.commit_group.sync.aligned;" ::: "memory"); }
template <int N> __device__ __forceinline__ void wg_wait() { asm volatile("wgmma.wait_group.sync.aligned %0;" ::"n"(N) : "memory"); }
template <int N> __device__ __forceinline__ void reg_fence(float (&d)[N]) {
#pragma unroll
    for (int i = 0; i < N; i++) asm volatile("" : "+f"(d[i])::"memory");
}
template<int TA,int TB> __device__ __forceinline__ void wgmma_n88(float (&d)[44], uint64_t da, uint64_t db, int scale_d){
  asm volatile("{.reg .pred p; setp.ne.b32 p,%46,0;\n"
  "wgmma.mma_async.sync.aligned.m64n88k16.f32.bf16.bf16 {%0,%1,%2,%3,%4,%5,%6,%7,%8,%9,%10,%11,%12,%13,%14,%15,%16,%17,%18,%19,%20,%21,%22,%23,%24,%25,%26,%27,%28,%29,%30,%31,%32,%33,%34,%35,%36,%37,%38,%39,%40,%41,%42,%43},%44,%45,p,1,1,%47,%48;}\n"
  :"+f"(d[0]),"+f"(d[1]),"+f"(d[2]),"+f"(d[3]),"+f"(d[4]),"+f"(d[5]),"+f"(d[6]),"+f"(d[7]),"+f"(d[8]),"+f"(d[9]),"+f"(d[10]),"+f"(d[11]),"+f"(d[12]),"+f"(d[13]),"+f"(d[14]),"+f"(d[15]),"+f"(d[16]),"+f"(d[17]),"+f"(d[18]),"+f"(d[19]),"+f"(d[20]),"+f"(d[21]),"+f"(d[22]),"+f"(d[23]),"+f"(d[24]),"+f"(d[25]),"+f"(d[26]),"+f"(d[27]),"+f"(d[28]),"+f"(d[29]),"+f"(d[30]),"+f"(d[31]),"+f"(d[32]),"+f"(d[33]),"+f"(d[34]),"+f"(d[35]),"+f"(d[36]),"+f"(d[37]),"+f"(d[38]),"+f"(d[39]),"+f"(d[40]),"+f"(d[41]),"+f"(d[42]),"+f"(d[43]):"l"(da),"l"(db),"r"(scale_d),"n"(TA),"n"(TB));
}
template<int TA,int TB> __device__ __forceinline__ void wgmma_n128(float (&d)[64], uint64_t da, uint64_t db, int scale_d){
  asm volatile("{.reg .pred p; setp.ne.b32 p,%66,0;\n"
  "wgmma.mma_async.sync.aligned.m64n128k16.f32.bf16.bf16 {%0,%1,%2,%3,%4,%5,%6,%7,%8,%9,%10,%11,%12,%13,%14,%15,%16,%17,%18,%19,%20,%21,%22,%23,%24,%25,%26,%27,%28,%29,%30,%31,%32,%33,%34,%35,%36,%37,%38,%39,%40,%41,%42,%43,%44,%45,%46,%47,%48,%49,%50,%51,%52,%53,%54,%55,%56,%57,%58,%59,%60,%61,%62,%63},%64,%65,p,1,1,%67,%68;}\n"
  :"+f"(d[0]),"+f"(d[1]),"+f"(d[2]),"+f"(d[3]),"+f"(d[4]),"+f"(d[5]),"+f"(d[6]),"+f"(d[7]),"+f"(d[8]),"+f"(d[9]),"+f"(d[10]),"+f"(d[11]),"+f"(d[12]),"+f"(d[13]),"+f"(d[14]),"+f"(d[15]),"+f"(d[16]),"+f"(d[17]),"+f"(d[18]),"+f"(d[19]),"+f"(d[20]),"+f"(d[21]),"+f"(d[22]),"+f"(d[23]),"+f"(d[24]),"+f"(d[25]),"+f"(d[26]),"+f"(d[27]),"+f"(d[28]),"+f"(d[29]),"+f"(d[30]),"+f"(d[31]),"+f"(d[32]),"+f"(d[33]),"+f"(d[34]),"+f"(d[35]),"+f"(d[36]),"+f"(d[37]),"+f"(d[38]),"+f"(d[39]),"+f"(d[40]),"+f"(d[41]),"+f"(d[42]),"+f"(d[43]),"+f"(d[44]),"+f"(d[45]),"+f"(d[46]),"+f"(d[47]),"+f"(d[48]),"+f"(d[49]),"+f"(d[50]),"+f"(d[51]),"+f"(d[52]),"+f"(d[53]),"+f"(d[54]),"+f"(d[55]),"+f"(d[56]),"+f"(d[57]),"+f"(d[58]),"+f"(d[59]),"+f"(d[60]),"+f"(d[61]),"+f"(d[62]),"+f"(d[63]):"l"(da),"l"(db),"r"(scale_d),"n"(TA),"n"(TB));
}
__device__ __forceinline__ void load_w1(const CUtensorMap* tm, uint32_t sb, int p0, int p1, int ft, int r, uint32_t gap = 0) {
    const int fm = 352 * (ft >> 2) + 64 * (ft & 3), fw = 352 * (ft >> 2) + 256 + ((24 * (ft & 3)) & ~15);
#pragma unroll 1
    for (int p = p0; p < p1; p++) {
        const uint32_t bar = sb + SM_BAR + 8 * (B_W1 + p), dst = sb + SM_W + (p == 7 ? 0 : p) * 24576;
        mbar_expect(bar, 24576);
#pragma unroll
        for (int e = 0; e < 2; e++) {
            asm volatile("cp.async.bulk.tensor.5d.shared::cluster.global.mbarrier::complete_tx::bytes [%0],[%1,{%2,%3,%3,%3,%4}],[%5];"
                         ::"r"(dst + e * 8192), "l"(tm + e), "r"(fm), "r"(0), "r"(64 * r + 8 * p + 4 * e), "r"(bar) : "memory");
            pause(gap);
        }
        asm volatile("cp.async.bulk.tensor.4d.shared::cluster.global.mbarrier::complete_tx::bytes [%0],[%1,{%2,%3,%3,%4}],[%5];"
                     ::"r"(dst + 16384), "l"(tm + 2), "r"(fw), "r"(0), "r"(64 * r + 8 * p), "r"(bar) : "memory");
    }
}
__device__ __forceinline__ int w2_slot(int kb) { return kb < 8 ? kb + 3 : kb - 8; }
__device__ __forceinline__ void load_w2(const CUtensorMap* tm, uint32_t sb, int k0, int k1, int s0, int r, uint32_t gap = 0) {
#pragma unroll 1
    for (int kb = k0; kb < k1; kb++) {
        const uint32_t bar = sb + SM_BAR + 8 * (B_W2 + kb);
        if (kb > k0) pause(gap);
        mbar_expect(bar, 16384);
        asm volatile("cp.async.bulk.tensor.3d.shared::cluster.global.mbarrier::complete_tx::bytes [%0],[%1,{%2,%3,%4}],[%5];"
                     ::"r"(sb + SM_W + w2_slot(kb) * 16384), "l"(tm), "r"(0), "r"(704 * r + 64 * kb), "r"(s0 >> 6), "r"(bar) : "memory");
    }
}
__device__ __forceinline__ const uint4* item_src(const uint4* hn, const uint4* u, int n, int dkeep, int r) {
    const bool g2 = n >= 32;
    const int LEAD = g2 ? LEAD2 : LEAD1, NB = g2 ? 11 : 16, m = g2 ? n - 32 : n, o = m - LEAD;
    int who, kb;
    if (m < LEAD) { who = 0; kb = m; }
    else if (m >= 2 * NB - LEAD) { who = 1; kb = m - NB; }
    else { who = (o & 1) ^ 1; kb = (o >> 1) + ((o & 1) ? LEAD : 0); }
    return (g2 ? u : hn) + (((dkeep ^ who ^ 1) * 2 + r) * NB + kb) * 512;
}

template <bool G2, int NACC>
__device__ __forceinline__ void mainloop(float (&acc)[NACC], uint32_t sb, int wg, int lane, int toff) {
    constexpr int NB = G2 ? 11 : 16;
    constexpr int N0 = G2 ? 32 : 0, LEAD = G2 ? LEAD2 : LEAD1;
    const uint64_t da0 = G2 ? mkdesc(sb + SM_RING, 16, 1024, 1) : mkdesc(sb + SM_RING, 8192, 1024, 1);
    const uint64_t db0 = G2 ? mkdesc(sb + SM_W, 8192, 1024, 1) : mkdesc(sb + SM_W, 16384 + toff, 1024, 1);
    uint32_t slot = wg ? (N0 + LEAD) % NSLOT : N0 % NSLOT, par = wg ? ((N0 + LEAD) / NSLOT) & 1 : (N0 / NSLOT) & 1;
    uint32_t fb = sb + SM_BAR + 8 * (B_FULL + slot), wb = sb + SM_BAR + 8 * (G2 ? B_W2 : B_W1), pend = 0;
    uint64_t da = da0 + slot * 512, db = db0 + (G2 ? w2_slot(0) * 1024 : 0);
    const int solo_lo = wg ? NB - LEAD : 0, solo_n = wg ? LEAD : LEAD - 1;
#pragma unroll 1
    for (int kb = 0; kb < NB; kb++) {
        const uint32_t eb = fb + 8 * (B_EMPTY - B_FULL);
        const bool k0 = mbar_test(wb, 0), k1 = mbar_test(eb, par ^ 1), k2 = mbar_try(fb, par);
        if (!(k0 & k1 & k2)) { mbar_wait(wb, 0); mbar_wait(eb, par ^ 1); mbar_wait(fb, par); }
        if ((threadIdx.x & 127) == 0) TSX(96 + wg * 32 + (G2 ? 16 : 0) + kb);
        wg_fence();
#pragma unroll
        for (int ks = 0; ks < 4; ks++) {
            if constexpr (G2) wgmma_n128<0, 1>(acc, da + ks * 2, db + ks * 128, (kb | ks) != 0);
            else wgmma_n88<1, 1>(acc, da + ks * 128, db + ks * 128, (kb | ks) != 0);
        }
        wg_commit();
        const bool solo = (unsigned)(kb - solo_lo) < (unsigned)solo_n;
        slot += solo ? 1 : 2;
        if (slot >= NSLOT) { slot -= NSLOT; par ^= 1; }
        fb = sb + SM_BAR + 8 * (B_FULL + slot); wb += G2 ? 8 : 8 * (kb & 1);
        da = da0 + slot * 512;
        if constexpr (G2) db = db0 + w2_slot(kb + 1) * 1024;
        else db = kb & 1 ? db0 + (kb + 1 >= W1_RES ? 0 : (kb + 1) * 768) : db - ((508 << 16) - 512);
        asm volatile("" : "+l"(da), "+l"(db), "+r"(fb), "+r"(par));
        wg_wait<1>();
        if (lane == 0 && pend) mbar_arrive(pend);
        if (lane == 0 && kb == 4) mbar_arrive(sb + SM_BAR + 8 * B_K3);
        pend = eb;
    }
    wg_wait<0>();
    reg_fence(acc);
    if (lane == 0) mbar_arrive(pend);
}
__device__ __forceinline__ void st_async4(uint32_t a, uint32_t x, uint32_t y, uint32_t z, uint32_t w, uint32_t bar) {
    asm volatile("{.reg .pred p; setp.ne.b32 p,%5,0; @p st.async.weak.shared::cluster.mbarrier::complete_tx::bytes.v4.b32 [%0],{%1,%2,%3,%4},[%5];}"
                 ::"r"(a), "r"(x), "r"(y), "r"(z), "r"(w), "r"(bar) : "memory");
}
template <bool TR> __device__ __forceinline__ void stsm4(bool live, uint32_t a, uint32_t x, uint32_t y, uint32_t z, uint32_t w) {
    if constexpr (TR) asm volatile("{.reg .pred p; setp.ne.b32 p,%5,0; @p stmatrix.sync.aligned.m8n8.x4.trans.shared.b16 [%0],{%1,%2,%3,%4};}" ::"r"(a), "r"(x), "r"(y), "r"(z), "r"(w), "r"((int)live) : "memory");
    else asm volatile("{.reg .pred p; setp.ne.b32 p,%5,0; @p stmatrix.sync.aligned.m8n8.x4.shared.b16 [%0],{%1,%2,%3,%4};}" ::"r"(a), "r"(x), "r"(y), "r"(z), "r"(w), "r"((int)live) : "memory");
}
__device__ __forceinline__ void sts32p(bool live, uint32_t a, uint32_t x) { asm volatile("{.reg .pred p; setp.ne.b32 p,%2,0; @p st.shared.u32 [%0],%1;}" ::"r"(a), "r"(x), "r"((int)live) : "memory"); }
__device__ __forceinline__ void sts64p(bool live, uint32_t a, uint32_t x, uint32_t y) {
    asm volatile("{.reg .pred p; setp.ne.b32 p,%3,0; @p st.shared.v2.u32 [%0],{%1,%2};}" ::"r"(a), "r"(x), "r"(y), "r"((int)live) : "memory");
}
__device__ __forceinline__ void stg128(bool live, void* p, uint4 v) {
    asm volatile("{.reg .pred p; setp.ne.b32 p,%5,0; @p st.global.v4.u32 [%0],{%1,%2,%3,%4};}" ::"l"(p), "r"(v.x), "r"(v.y), "r"(v.z), "r"(v.w), "r"((int)live) : "memory");
}
__device__ __forceinline__ float gelu_t(float x) {
    float p = fmaf(x * x, 0.044715f * 0.7978845608028654f, 0.7978845608028654f) * x, th;
    asm("tanh.approx.f32 %0,%1;" : "=f"(th) : "f"(p));
    float hx = 0.5f * x;
    return fmaf(hx, th, hx);
}

__device__ __forceinline__ void epi1_help(uint32_t sb, int part, int wq, int lane, uint4* u, int c0, bool live) {
    const uint32_t ra = sb + SM_W + 36864 + wq * 2816 + part * 1024, da = sb + SM_RING + 24576 + (wq * 3 + part) * 2048;
    uint4* up[2];
#pragma unroll
    for (int k = 0; k < 2; k++) { int rr = (lane >> 2) + 8 * k, c = c0 + (lane & 3); up[k] = u + (c >> 3) * 512 + (16 * wq + rr) * 8 + ((c ^ rr) & 7); }
    if (live) mbar_wait_cluster(sb + SM_BAR + 8 * B_RECV, 0);
    TS(4);
    const uint4 q0 = lds128(ra + lane * 16);
    const uint2 q1 = lds64(ra + 512 + lane * (part == 2 ? 8 : 16)), q2 = lds64(ra + 520 + lane * (part == 2 ? 0 : 16));
    uint32_t v[8] = {q0.x, q0.y, q0.z, q0.w, q1.x, q1.y, q2.x, q2.y};
    if (live) BAR_SYNC(9, 512);
#pragma unroll
    for (int c = 0; c < 4; c++) {
        const uint4 a = lds128(da + c * 512 + lane * 16);
        v[2 * c] = pack2(gelu_t(__uint_as_float(a.x) + blo(v[2 * c])), gelu_t(__uint_as_float(a.y) + bhi(v[2 * c])));
        v[2 * c + 1] = pack2(gelu_t(__uint_as_float(a.z) + blo(v[2 * c + 1])), gelu_t(__uint_as_float(a.w) + bhi(v[2 * c + 1])));
    }
    __syncwarp();
#pragma unroll
    for (int j = 0; j < 2; j++)
        stsm4<false>(live, da + (lane & 15) * 80 + (lane >> 4) * 16 + j * 32, v[4 * j], v[4 * j + 1], v[4 * j + 2], v[4 * j + 3]);
    __syncwarp();
#pragma unroll
    for (int k = 0; k < 2; k++) stg128(live && (part < 2 || (lane & 3) < 3), up[k], lds128(da + ((lane >> 2) + 8 * k) * 80 + (lane & 3) * 16));
    if (live) BAR_ARRIVE(1, 416);
    TS(26);
}

struct Maps { uint4 *Y, *hn, *u; uint2* Y128; float2* st; unsigned* cnt; CUtensorMap m[6]; };

__global__ void __cluster_dims__(2, 1, 1) __launch_bounds__(NTHR, 1)
fused_kernel(const __nv_bfloat16* __restrict__ x, const __nv_bfloat16* __restrict__ w1, const __nv_bfloat16* __restrict__ w2,
             const __nv_bfloat16* __restrict__ b1, const __nv_bfloat16* __restrict__ b2, __nv_bfloat16* out, const __grid_constant__ Maps tm) {
    extern __shared__ __align__(1024) unsigned char smem[];
    const uint32_t sb = (uint32_t)__cvta_generic_to_shared(smem);
    const int tid = threadIdx.x, w0 = __shfl_sync(~0u, tid >> 5, 0), w = w0 == 17 ? 1 : w0, lane = tid & 31, g = lane >> 2, t = lane & 3, b = blockIdx.x;
    TS(0);
    const int cg = 4 * (g >> 1) + (g & 1);
    const int r = b & 1, dt = (b >> 1) & 3, ft = b >> 3, dkeep = 2 * dt + r;
    const int row = w * 128 + b;
    uint2 d[4] = {};
    if (w0 < 16) {
        const uint32_t* xp = (const uint32_t*)(x + (size_t)row * 512) + 64 * t + 2 * g;
#pragma unroll
        for (int i = 0; i < 4; i++) asm volatile("ld.global.nc.v2.u32 {%0,%1},[%2];" : "=r"(d[i].x), "=r"(d[i].y) : "l"(xp + 16 * i));
    }
    uint32_t peer;
    asm("mapa.shared::cluster.u32 %0,%1,%2;" : "=r"(peer) : "r"(sb), "r"(r ^ 1));
    if (w == 18) {
        if (lane < 4) asm volatile("prefetch.tensormap [%0];" ::"l"(tm.m + lane) : "memory");
        if (lane == 0) {
#pragma unroll
            for (int i = 0; i < B_COUNT; i++)
                if (i != B_WF) mbar_init(sb + SM_BAR + 8 * i, i >= B_G1DONE ? 8 : i == B_TAIL ? 2 : (i >= B_EMPTY && i < B_W1) ? 4 : 1);
            mbar_expect(sb + SM_BAR + 8 * B_RECV, 11264);
            mbar_expect(sb + SM_BAR + 8 * (B_RECV + 1), 16384);
            asm volatile("fence.mbarrier_init.release.cluster;" ::: "memory");
            asm volatile("fence.proxy.async.shared::cta;" ::: "memory");
        }
        __syncwarp();
        BAR_ARRIVE(6, 608);
        BAR_SYNC(8, 64);
        if (lane == 0) {
            paced_prefetch((const char*)w1 + b * 44032, GAP1);
            mbar_wait(sb + SM_BAR + 8 * B_GO, 0);
            load_w1(tm.m, sb, NW0, NW0 + NW1, ft, r);
            mbar_wait(sb + SM_BAR + 8 * (B_GO + 1), 0);
            load_w1(tm.m, sb, NW0 + NW1, NW0 + NW1 + NW2, ft, r);
            mbar_wait(sb + SM_BAR + 8 * (B_GO + 3), 0);
            load_w1(tm.m, sb, NW0 + NW1 + NW2, NW0 + NW1 + NW2 + NW3, ft, r);
            mbar_wait(sb + SM_BAR + 8 * (B_GO + 2), 0);
            load_w1(tm.m, sb, NW0 + NW1 + NW2 + NW3, 7, ft, r, GC);
            paced_prefetch((const char*)w2 + b * 44032, GAP2);
            mbar_wait(sb + SM_BAR + 8 * B_K3, 0);
            asm volatile("mbarrier.arrive.relaxed.cluster.shared::cluster.b64 _,[%0];" ::"r"(peer + SM_BAR + 8 * B_RFREE) : "memory");
            load_w1(tm.m, sb, 7, 8, ft, r, GA);
            mbar_wait(sb + SM_BAR + 8 * B_TAIL, 0);
            load_w2(tm.m + 3, sb, 0, 4, 128 * ft, r);
            mbar_wait(sb + SM_BAR + 8 * B_G1DONE, 0);
            TSX(21);
            load_w2(tm.m + 3, sb, 4, W2A, 128 * ft, r);
            mbar_wait(sb + SM_BAR + 8 * B_EPI, 0);
            load_w2(tm.m + 3, sb, W2A, W2B, 128 * ft, r);
            TSX(27);
            mbar_wait(sb + SM_BAR + 8 * B_S4, 0);
            load_w2(tm.m + 3, sb, W2B, 11, 128 * ft, r, GB);
            mbar_wait(sb + SM_BAR + 8 * B_K3, 1);
            asm volatile("mbarrier.arrive.relaxed.cluster.shared::cluster.b64 _,[%0];" ::"r"(peer + SM_BAR + 8 * (B_RFREE + 1)) : "memory");
        }
        return;
    }
    const bool live = w0 != 17;
    unsigned tgt = 0;
    if (!live) {
        if (lane == 0) {
            mbar_init(sb + SM_BAR + 8 * B_WF, 1); mbar_expect(sb + SM_BAR + 8 * B_WF, 32768);
            asm volatile("fence.proxy.async.shared::cta;" ::: "memory");
#pragma unroll
            for (int a = 0; a < 4; a++) {
                int c0 = (a & 2) ? ((16 - ft) & 15) * 257 + 240 - 16 * (b & 7) : ft * 257 + 16 * (b & 7);
                asm volatile("cp.async.bulk.tensor.2d.shared::cluster.global.mbarrier::complete_tx::bytes [%0],[%1,{%2,%3}],[%4];"
                             ::"r"(sb + SM_WS + a * 8192), "l"(tm.m + 4 + (a & 1)), "r"(c0 & ~15), "r"(0), "r"(sb + SM_BAR + 8 * B_WF) : "memory");
            }
        }
        __syncwarp();
        BAR_ARRIVE(8, 64);
        BAR_ARRIVE(0, 576);
        if (lane < 3) asm volatile("ld.relaxed.gpu.global.u32 %0,[%1];" : "=r"(tgt) : "l"(&tm.cnt[32 * (lane < 2 ? 3 + 2 * (dkeep ^ lane) + r : 1 + r)]) : "memory");
        if (lane < 2 && b < 32) asm volatile("prefetch.global.L2 [%0];" ::"l"(lane ? (const char*)b2 + b * 128 : (const char*)b1 + min(b, 21) * 128) : "memory");
    }
    const int sg1 = (b & 3) | ((b >> 3) & 12);
    uint4* y1 = tm.Y + ((g * 8 + (w >> 1)) * 128 + b) * 8 + ((4 * (w & 1) + t) ^ (sg1 >> 1));
    uint2* y1x = tm.Y128 + (g * 128 + b) * 4 + t;
    if (w0 < 16) {
        const int q = w & 3, st = w >> 2;
        uint32_t A[2], B[2];
#pragma unroll
        for (int e = 0; e < 2; e++) {
            int k = st == 0 ? (cg + 2 * e) * (4 * t + q) * 128 : st == 1 ? -8 * (4 * t + 2 * e + (q >> 1)) * (cg + 2 * (q & 1))
                  : 128 * (g + 8 * e) * (4 * t + q) + b * (st == 2 ? g + 8 * e : 4 * t + q);
            float c, s;
            cs<11>(k, c, s);
            A[e] = pack2(c, s); B[e] = pack2(-s, c);
        }
        uint32_t a = sb + SM_TB + st * 2048 + (q >> 1) * 512 + lane * 16 + (q & 1) * 8;
        sts64(a, A[0], A[1]); sts64(a + 1024, B[0], B[1]);
    }
    if (live) BAR_SYNC(5, 544);
    uint4 F[4], T[4];
    const uint32_t tb = sb + SM_TB + lane * 16;
    ldtab(F, tb);
    float re[2][4], im[2][4];
    const int j1 = ft, mcol = 16 * (b & 7) + w;
    if (w < 16) {
        ldtab(T, tb + 2048);
        uint32_t off[8];
#pragma unroll
        for (int k = 0; k < 8; k++) {
            int m = 16 * (cg + 2 * (k >> 2)) + 4 * t + (k & 3);
            int p = m < 128 ? m : 256 - m;
            int f = ((p >> 4) & 1) | ((p >> 5) & 2);
            off[k] = sb + SM_XB + w * 1032 + (p ^ f) * 8 + (m < 128 ? 0 : 4);
            asm volatile("" : "+r"(off[k]));
        }
        float s1 = rowsum(d[0].x, d[1].x, d[0].y, d[1].y, d[2].x, d[3].x, d[2].y, d[3].y);
        dft16(re, im, F, d);
        TS(1);
        float dc = g == 0 ? s1 * (-1.f / 32) : 0.f;
#pragma unroll
        for (int k = 0; k < 4; k++) { re[k >> 1][k & 1] += dc; im[k >> 1][k & 1] += dc; }
        rowtw(re, im, T, d);
        float rs = rsqrtf(fmaf(sumsq(re, im), 1.f / (16 * 512), 1e-5f));
        dft16(re, im, F, d);
        const uint32_t sc = pack2(rs, g < 4 ? rs : -rs);
#pragma unroll
        for (int k = 0; k < 8; k++) {
            int H = k >> 2, cc = k & 3;
            uint32_t val = hmul(pack2(re[cc >> 1][2 * H + (cc & 1)], im[cc >> 1][2 * H + (cc & 1)]), sc);
            sts32p(live, off[k], val);
            if (k == 0) sts32p(live && (lane & 15) == 0, off[0] ^ 4, val ^ 0x80000000u);
        }
    } else {
        float c0, s0, c1, s1, c2, s2, c3, s3;
        cs<7>(cg * 2 * t, c0, s0); cs<7>(cg * (2 * t + 1), c1, s1); cs<7>((cg + 2) * 2 * t, c2, s2); cs<7>((cg + 2) * (2 * t + 1), c3, s3);
        sts128(sb + SM_TB + 8192 + lane * 16, make_uint4(pack2(c0, c1), pack2(c2, c3), pack2(s0, s1), pack2(s2, s3)));
        cs<3>(2 * t * g, c0, s0); cs<3>((2 * t + 1) * g, c1, s1);
        sts128(sb + SM_TB + 8704 + lane * 16, make_uint4(pack2(c0, c1), pack2(s0, s1), pack2(-s0, -s1), 0));
        cs<9>(16 * (b & 7) + lane, c0, s0);
        const float sc = 0.5f / (2048.f * 256.f);
        c0 *= sc; c1 = fmaf(-s0, sc, sc); s1 = fmaf(s0, sc, sc);
        sts128(sb + SM_TB + 9216 + lane * 16, make_uint4(pack2(c1, c1), pack2(s1, s1), pack2(c0, c0), 0));
    }
    ldtab(T, tb + 4096);
    {
        int blk = w >> 1, f = (blk & 1) | ((blk >> 1) & 2);
        uint32_t a = sb + SM_XB + 4 * t * 1032 + ((8 * w + g) ^ f ^ (w < 16 ? sg1 & 1 : 0)) * 8;
        if (live) BAR_SYNC(0, 576);
#pragma unroll
        for (int i = 0; i < 4; i++) d[i] = lds64(a + i * 1032);
        dft16(re, im, T, d);
#pragma unroll
        for (int H = 0; H < 2; H++) {
            uint4 o = make_uint4(pack2(re[0][2 * H], im[0][2 * H]) | 1, pack2(re[1][2 * H], im[1][2 * H]),
                                 pack2(re[0][2 * H + 1], im[0][2 * H + 1]) | 1, pack2(re[1][2 * H + 1], im[1][2 * H + 1]));
            stg128(w0 < 16, y1 + H * 64 * 128 * 8, o);
            if (w == 16) y1x[H * 8 * 128 * 4] = make_uint2(o.x, o.y);
        }
    }
    TS(2);
    if (w < 16) {
        int a = lane >> 3, i = lane & 7, j2 = (w & 12) + (i >> 2) + (i & 2) + 16 * (2 * (w & 3) + (i & 1));
        int rw = a < 2 ? j2 : (128 - (j1 != 0) - j2) & 127;
        int mis = (a < 2 ? j1 : -j1) & 15;
        if (live) mbar_wait(sb + SM_BAR + 8 * B_WF, 0);
        TS(29);
#pragma unroll
        for (int hc = 0; hc < 3; hc++) {
            uint32_t q0, q1, q2, q3;
            asm volatile("ldmatrix.sync.aligned.m8n8.x4.trans.shared.b16 {%0,%1,%2,%3},[%4];" : "=r"(q0), "=r"(q1), "=r"(q2), "=r"(q3)
                         : "r"(sb + SM_WS + a * 8192 + rw * 64 + ((((mis >> 3) + hc) ^ (rw >> 1)) & 3) * 16) : "memory");
            int c = 8 * hc + i - (mis & 7);
            c = (unsigned)c <= 16u ? (a < 2 ? c : 16 - c) : 17;
            stsm4<false>(live, sb + SM_WT + c * 1040 + a * 256 + w * 16, q0, q1, q2, q3);
        }
    }
    const uint4 ka = lds128(tb + 8192), kb4 = lds128(tb + 8704), kc4 = lds128(sb + SM_TB + 9216 + w * 16);
    const uint32_t pc[2] = {ka.x, ka.y}, ps[2] = {ka.z, ka.w}, c8 = kb4.x, s8 = kb4.y, n8 = kb4.z, km = kc4.x, kp = kc4.y, kc = kc4.z;
    if (live) BAR_SYNC(6, 608);
    else {
        if (lane < 3) sts32(sb + SM_BAR + 8 * B_COUNT + 4 * lane, (tgt | (lane < 2 ? 7 : 63)) + 1);
        __syncwarp();
        BAR_ARRIVE(6, 608);
    }
    TS(28);
    if (w < 16 || mcol == 128) {
        const uint4* yp = tm.Y + (size_t)b * 1024 + tid;
        const uint2* yq = tm.Y128 + (j1 * 128 + 32 * t + g) * 4;
        uint4 ya, yb;
        if (w0 < 16) { ya = ldv128(yp); yb = ldv128(yp + 512); }
        uint32_t alr[2], ali[2], acr[2], aci[2], ber[2], bei[2];
        {
            uint2 wv[4];
#pragma unroll
            for (int a = 0; a < 4; a++) wv[a] = lds64(sb + SM_WT + w * 1040 + a * 256 + ((g >> 1) * 4 + t) * 16 + (g & 1) * 8);
#pragma unroll
            for (int h = 0; h < 2; h++) {
                uint32_t pr = h ? wv[0].y : wv[0].x, pi = h ? wv[1].y : wv[1].x, qr = h ? wv[2].y : wv[2].x, qi = (h ? wv[3].y : wv[3].x) ^ 0x80008000u;
                alr[h] = hfma(pr, km, hmul(qr, kp)); ali[h] = hfma(pi, km, hmul(qi, kp));
                acr[h] = hfma(pr, kp, hmul(qr, km)); aci[h] = hfma(pi, kp, hmul(qi, km));
                ber[h] = hfma(qi, kc, hneg(hmul(pi, kc))); bei[h] = hfma(pr, kc, hneg(hmul(qr, kc)));
                asm volatile("" : "+r"(alr[h]), "+r"(ali[h]), "+r"(acr[h]), "+r"(aci[h]), "+r"(ber[h]), "+r"(bei[h]));
            }
        }
        uint32_t ai = sb + SM_XB + (32 * t + g) * 128 + ((w ^ ((g & 3) | (t << 2))) * 8);
        uint32_t ao = sb + SM_WT + (8 * cg + 2 * t) * 128 + ((w ^ (t | ((g & 3) << 2))) * 8);
        asm volatile("" : "+r"(ai), "+r"(ao));
        if (w < 16) {
            if (live) {
                for (int it = 0; !(ya.x & yb.x & 1) && it < (1 << 16); it++) {
                    if (!(ya.x & 1)) ya = ldv128(yp);
                    if (!(yb.x & 1)) yb = ldv128(yp + 512);
                }
                sts128(sb + SM_XB + tid * 16, ya); sts128(sb + SM_XB + tid * 16 + 8192, yb);
                BAR_SYNC(3, 512);
            }
            TS(5);
            if (tid == 0) mbar_arrive(sb + SM_BAR + 8 * B_GO);
#pragma unroll
            for (int i = 0; i < 4; i++) d[i] = lds64(ai + i * 1024);
        } else {
            int it = 0;
            do {
#pragma unroll
                for (int i = 0; i < 4; i++) d[i] = ldv64(yq + 32 * i);
            } while (!(d[0].x & d[1].x & d[2].x & d[3].x & 1) && ++it < (1 << 16));
            __syncwarp();
        }
        dft16(re, im, F, d);
        float zr[2][4], zi[2][4];
#pragma unroll
        for (int tau = 0; tau < 2; tau++) {
            uint32_t R0 = pack2(re[tau][0], re[tau][1]), R1 = pack2(re[tau][2], re[tau][3]), I0 = pack2(im[tau][0], im[tau][1]), I1 = pack2(im[tau][2], im[tau][3]);
            uint32_t a0 = hfma(I0, ps[0], hmul(R0, pc[0])), a1 = hfma(I1, ps[1], hmul(R1, pc[1]));
            uint32_t a2 = hfma(hneg(R0), ps[0], hmul(I0, pc[0])), a3 = hfma(hneg(R1), ps[1], hmul(I1, pc[1]));
            mma0(zr[tau], a0, a1, a2, a3, c8, s8);
            mma0(zi[tau], a0, a1, a2, a3, n8, c8);
        }
        uint32_t fa[2][4];
#pragma unroll
        for (int h = 0; h < 2; h++) {
            uint32_t mr = pack2(zr[0][2 * h], zr[0][2 * h + 1]), mi = pack2(zi[0][2 * h], zi[0][2 * h + 1]);
            uint32_t qr = pack2(zr[1][2 * h], zr[1][2 * h + 1]), qi = pack2(zi[1][2 * h], zi[1][2 * h + 1]);
            fa[0][2 + h] = hfma(alr[h], mr, hfma(hneg(ali[h]), mi, hfma(ber[h], qr, hmul(hneg(bei[h]), qi))));
            fa[0][h] = hfma(alr[h], mi, hfma(ali[h], mr, hfma(ber[h], qi, hmul(bei[h], qr))));
            fa[1][2 + h] = hfma(acr[h], qr, hfma(hneg(aci[h]), qi, hfma(hneg(ber[h]), mr, hmul(bei[h], mi))));
            fa[1][h] = hfma(acr[h], qi, hfma(aci[h], qr, hfma(hneg(ber[h]), mi, hmul(hneg(bei[h]), mr))));
        }
#pragma unroll
        for (int tau = 0; tau < 2; tau++) {
            mma0(zr[tau], fa[tau][0], fa[tau][1], fa[tau][2], fa[tau][3], c8, s8);
            mma0(zi[tau], fa[tau][0], fa[tau][1], fa[tau][2], fa[tau][3], n8, c8);
        }
#pragma unroll
        for (int tau = 0; tau < 2; tau++)
#pragma unroll
            for (int h = 0; h < 2; h++) {
                uint32_t R0 = pack2(zr[tau][2 * h], zr[tau][2 * h + 1]), I0 = pack2(zi[tau][2 * h], zi[tau][2 * h + 1]);
                uint32_t R = hfma(I0, ps[h], hmul(R0, pc[h])), I = hfma(hneg(R0), ps[h], hmul(I0, pc[h]));
                asm("movmatrix.sync.aligned.m8n8.trans.b16 %0,%0;" : "+r"(R));
                asm("movmatrix.sync.aligned.m8n8.trans.b16 %0,%0;" : "+r"(I));
                uint32_t lo = __byte_perm(R, I, 0x5410), hi = __byte_perm(R, I, 0x7632);
                if (tau) { d[2 * h].y = lo; d[2 * h + 1].y = hi; } else { d[2 * h].x = lo; d[2 * h + 1].x = hi; }
            }
        dft16(re, im, F, d);
        if (w < 16) {
#pragma unroll
            for (int xx = 0; xx < 4; xx++)
                sts64p(live, ao + (16 * (xx >> 1) + (xx & 1)) * 128, pack2(re[0][xx], im[0][xx]) & ~1u, pack2(re[1][xx], im[1][xx]));
            if (live) BAR_SYNC(3, 512);
#pragma unroll
            for (int k = 0; k < 2; k++) stg128(live, (uint4*)yp + 512 * k, lds128(sb + SM_WT + (tid + 512 * k) * 16));
        } else {
#pragma unroll
            for (int xx = 0; xx < 4; xx++) tm.Y128[(j1 * 128 + 8 * cg + 2 * t + 16 * (xx >> 1) + (xx & 1)) * 4].x = pack2(re[0][xx], im[0][xx]) & ~1u;
        }
    }
    TS(6);
    {
        uint4 xr[2];
#pragma unroll
        for (int H = 0; H < 2; H++) asm volatile("ld.global.nc.v4.u32 {%0,%1,%2,%3},[%4];" : "=r"(xr[H].x), "=r"(xr[H].y), "=r"(xr[H].z), "=r"(xr[H].w)
                                                 : "l"((const uint4*)(x + (size_t)(row & 2047) * 512) + 4 * (cg + 2 * H) + t));
        ldtab(T, tb + 6144);
        const int sg = ((b >> 1) & 3) | ((b >> 1) & 4) | ((b >> 2) & 8);
        const uint2* yp = w < 16 ? (const uint2*)tm.Y + ((size_t)(4 * t * 8 + (w >> 1)) * 128 + b) * 16 + ((8 * (w & 1) + g) ^ sg) : tm.Y128 + (4 * t * 128 + b) * 4;
        const int ys = w < 16 ? 8 * 128 * 16 : 512;
        const int m0 = 8 * w + 2 * t, q0 = 256 - m0, q1 = 255 - m0;
        const uint32_t rb = sb + SM_XB + g * 1056;
        uint32_t o0 = rb + (m0 ^ ((m0 >> 6) << 3)) * 4, o1 = rb + (q0 ^ (((q0 >> 6) & 3) << 3)) * 4, o2 = rb + (q1 ^ ((q1 >> 6) << 3)) * 4;
        uint32_t ai = sb + SM_XB + w * 1056 + ((64 * t + 2 * g) ^ ((t & 1) << 3)) * 4;
        uint4* np = tm.hn + (2 * (g >> 1) * 32 + ((b >> 2) ^ ((w >> 2) & 1))) * 512 + ((b & 3) * 16 + w) * 8 + ((4 * (g & 1) + t) ^ (w & 7));
        asm volatile("" : "+r"(o0), "+r"(o1), "+r"(o2), "+r"(ai));
        if (w == 16 && mcol != 128) mbar_wait(sb + SM_BAR + 8 * B_GO, 0);
        int it = 0;
        d[0].x = d[1].x = d[2].x = d[3].x = 1;
        __nanosleep(150);
        if (live) do {
#pragma unroll
            for (int i = 0; i < 4; i++)
                if (d[i].x & 1) d[i] = ldv64(yp + i * ys);
        } while (((d[0].x | d[1].x | d[2].x | d[3].x) & 1) && ++it < (1 << 16));
        __syncwarp();
        TS(8);
        dft16(re, im, T, d);
        ldtab(T, tb + 2048);
#pragma unroll
        for (int H = 0; H < 2; H++) {
            if (m0 == 0) {
                re[0][2 * H] = 0.5f * (re[0][2 * H] - re[1][2 * H]); im[0][2 * H] = 0.5f * (im[0][2 * H] + im[1][2 * H]);
            }
            uint32_t v0 = pack2(re[0][2 * H], im[0][2 * H]);
            if (w < 16) {
                sts64p(live, o0 + H * 8 * 1056, v0, pack2(re[0][2 * H + 1], im[0][2 * H + 1]));
                sts32p(live, o1 + H * 8 * 1056, pack2(-re[1][2 * H], im[1][2 * H]));
                sts32p(live, o2 + H * 8 * 1056, pack2(-re[1][2 * H + 1], im[1][2 * H + 1]));
            }
        }
        if (w == 16) {
            BAR_SYNC(7, 64);
            if (t == 0) { sts32(o0, pack2(re[0][0], im[0][0])); sts32(o0 + 8 * 1056, pack2(re[0][2], im[0][2])); }
            BAR_ARRIVE(5, 544);
            return;
        }
        float hr[2][4], hi[2][4];
#pragma unroll
        for (int k = 0; k < 8; k++) {
            int H = k >> 2, cc = k & 3;
            uint32_t xv = cc == 0 ? xr[H].x : cc == 1 ? xr[H].y : cc == 2 ? xr[H].z : xr[H].w;
            hi[cc >> 1][2 * H + (cc & 1)] = blo(xv); hr[cc >> 1][2 * H + (cc & 1)] = bhi(xv);
        }
        if (w == 0) BAR_ARRIVE(7, 64);
        if (live) BAR_SYNC(5, 544);
        TS(9);
        if (tid == 0) mbar_arrive(sb + SM_BAR + 8 * (B_GO + 1));
#pragma unroll
        for (int i = 0; i < 4; i++) d[i] = lds64(ai + ((16 * i) ^ ((t >> 1) << 4)) * 4);
        dft16(re, im, F, d);
        rowtw(re, im, T, d);
        dft16<true>(hr, hi, F, d);
        uint32_t hv[8];
#pragma unroll
        for (int k = 0; k < 8; k++) hv[k] = pack2(hi[(k >> 1) & 1][2 * (k >> 2) + (k & 1)], hr[(k >> 1) & 1][2 * (k >> 2) + (k & 1)]);
        float mean = rowsum(hv[0], hv[1], hv[2], hv[3], hv[4], hv[5], hv[6], hv[7]) * (1.f / 512);
        float s2 = sumsq(hr, hi);
        float var = fmaxf(fmaf(-mean, mean, s2 * (1.f / 512)), 0.f);
        float r1 = rsqrtf(var + 1e-5f), rs = r1 * rsqrtf(var * r1 * r1 + 1e-5f), nb = -mean * rs;
#pragma unroll
        for (int k = 0; k < 8; k++) hv[k] = pack2(fmaf(hi[(k >> 1) & 1][2 * (k >> 2) + (k & 1)], rs, nb), fmaf(hr[(k >> 1) & 1][2 * (k >> 2) + (k & 1)], rs, nb));
        if (live && lane < 4) tm.st[row * 4 + lane] = make_float2(mean, __frcp_rn(rs));
        stg128(live, np, make_uint4(hv[0], hv[1], hv[2], hv[3])); stg128(live, np + 32 * 512, make_uint4(hv[4], hv[5], hv[6], hv[7]));
    }
    TS(10);
    if (!live) {
        unsigned* cp = &tm.cnt[32 * (lane < 2 ? 3 + 2 * (dkeep ^ lane) + r : 1 + r)];
        asm volatile("ld.shared.u32 %0,[%1];" : "=r"(tgt) : "r"(sb + SM_BAR + 8 * B_COUNT + 4 * (lane & 3)) : "memory");
#pragma unroll 1
        for (int n0 = 0; n0 <= 32; n0 += 32) {
            const int slot = (n0 + lane) % NSLOT;
            const uint4* src = item_src(tm.hn, tm.u, n0 + lane, dkeep, r);
            if (n0) BAR_SYNC(1, 416); else BAR_SYNC(4, 544);
            if (lane == 0) { cnt_arrive(&tm.cnt[32 * (n0 ? 3 + 2 * dkeep + (ft >> 3) : 1 + (b >> 6))]); TSX(n0 ? 14 : 11); }
            if (lane == 0) mbar_arrive(sb + SM_BAR + 8 * (n0 ? B_EPI : B_GO + 3));
            if (n0) mbar_wait(sb + SM_BAR + 8 * B_G1DONE, 0);
            if (lane < NSLOT) mbar_expect(sb + SM_BAR + 8 * (B_FULL + slot), 8192);
            asm volatile("fence.proxy.async.shared::cta;" ::: "memory");
            if (n0 ? lane < 2 : lane == 2) cnt_wait(cp, tgt);
            __syncwarp();
            fence_async();
            if (lane == 0) TSX(n0 ? 22 : 20);
            if (lane < NSLOT) bulk_load(sb + SM_RING + slot * 8192, src, 8192, sb + SM_BAR + 8 * (B_FULL + slot));
            if (lane < NSLOT) TSX(32 + n0 + lane);
            __syncwarp();
            if (lane == 0) mbar_arrive(sb + SM_BAR + 8 * (n0 ? B_S4 : B_GO + 2));
        }
        return;
    }
    BAR_ARRIVE(4, 544);
    const int wg = w >> 2, wq = w & 3;
    if (wg < 2) {
        {
            float acc[44];
            uint32_t bb[11];
            const int cm = 44 * (ft >> 2) + 8 * (ft & 3), ct = 44 * (ft >> 2) + 24 + 3 * (ft & 3);
            if (wg == 0) {
#pragma unroll
                for (int j = 0; j < 11; j++) { int c = (j < 8 ? cm : ct) + j; bb[j] = c < 172 ? __ldg((const uint32_t*)b1 + 4 * c + t) : 0u; }
            }
            const uint32_t ra = SM_W + 36864 + wq * 2816;
            {
                constexpr bool live = true;
                if (live) {
                    mainloop<false>(acc, sb, wg, lane, (ft & 1) * 16);
                    if (lane == 0) mbar_arrive(sb + SM_BAR + 8 * B_G1DONE);
                }
                if (wg == 0) {
                    TS(12);
#pragma unroll
                    for (int i = 0; i < 44; i++) acc[i] += (i & 1) ? bhi(bb[i >> 2]) : blo(bb[i >> 2]);
                    if (live) mbar_wait_cluster(sb + SM_BAR + 8 * B_RFREE, 0);
                    const uint32_t bar = live ? peer + SM_BAR + 8 * B_RECV : 0;
#pragma unroll
                    for (int j = 0; j < 5; j++)
                        st_async4(peer + ra + j * 512 + lane * 16, pack2(acc[8 * j], acc[8 * j + 1]), pack2(acc[8 * j + 2], acc[8 * j + 3]),
                                  pack2(acc[8 * j + 4], acc[8 * j + 5]), pack2(acc[8 * j + 6], acc[8 * j + 7]), bar);
                    asm volatile("{.reg .pred p; setp.ne.b32 p,%3,0; @p st.async.weak.shared::cluster.mbarrier::complete_tx::bytes.v2.b32 [%0],{%1,%2},[%3];}"
                                 ::"r"(peer + ra + 2560 + lane * 8), "r"(pack2(acc[40], acc[41])), "r"(pack2(acc[42], acc[43])), "r"(bar) : "memory");
                    TS(3);
#pragma unroll 1
                    for (int go = 0; go < 2; go++) epi1_help(sb, 0, wq, lane, tm.u + dkeep * 22 * 512, cm, go);
                } else {
                    if (tid == 128) TSX(13);
                    if (lane < 3) mbar_wait(sb + SM_BAR + 8 * (B_EMPTY + 3 + lane), 0);
                    __syncwarp();
#pragma unroll
                    for (int c = 0; c < 11; c++)
                        sts128(sb + SM_RING + 24576 + wq * 6144 + c * 512 + lane * 16,
                               make_uint4(__float_as_uint(acc[4 * c]), __float_as_uint(acc[4 * c + 1]), __float_as_uint(acc[4 * c + 2]), __float_as_uint(acc[4 * c + 3])));
                    BAR_ARRIVE(9, 512);
                    if (tid == 128) TSX(15);
                }
            }
        }
        {
            float acc[64];
            const uint32_t ra = SM_W + 3 * 16384 + wq * 4096 + lane * 16;
            const uint32_t sa = sb + SM_W + 4 * 16384 + ((lane >> 4) * 8 + (lane & 7)) * 128 + (((2 * wq + ((lane >> 3) & 1)) ^ (lane & 7)) * 16);
            {
                constexpr bool live = true;
                if (live) mainloop<true>(acc, sb, wg, lane, 0);
                if (wg == 0) {
                    TS(16);
                    if (live) mbar_wait_cluster(sb + SM_BAR + 8 * (B_RFREE + 1), 0);
                    const uint32_t bar = live ? peer + SM_BAR + 8 * (B_RECV + 1) : 0;
#pragma unroll
                    for (int j = 0; j < 8; j++)
                        st_async4(peer + ra + j * 512, pack2(acc[8 * j], acc[8 * j + 1]), pack2(acc[8 * j + 2], acc[8 * j + 3]),
                                  pack2(acc[8 * j + 4], acc[8 * j + 5]), pack2(acc[8 * j + 6], acc[8 * j + 7]), bar);
                    TS(7);
                    if (live) mbar_wait_cluster(sb + SM_BAR + 8 * (B_RECV + 1), 0);
                    TS(25);
#pragma unroll
                    for (int j = 0; j < 8; j++) { uint4 q = lds128(sb + ra + j * 512); stsm4<true>(live, sa + 16384 + j * 2048, q.x, q.y, q.z, q.w); }
                    if (live) BAR_ARRIVE(10, 384);
                } else {
                    if (tid == 128) TSX(17);
                    if (live) mbar_wait(sb + SM_BAR + 8 * B_K3, 1);
#pragma unroll
                    for (int j = 0; j < 8; j++)
                        stsm4<true>(live, sa + j * 2048, pack2(acc[8 * j], acc[8 * j + 1]), pack2(acc[8 * j + 2], acc[8 * j + 3]),
                                    pack2(acc[8 * j + 4], acc[8 * j + 5]), pack2(acc[8 * j + 6], acc[8 * j + 7]));
                    if (live) BAR_ARRIVE(2, 384);
                    if (tid == 128) TSX(18);
                }
            }
        }
    } else {
        const int tt = tid - 256;
        uint4* op = (uint4*)(out + (size_t)(128 * ft + (tt >> 3)) * 512 + 64 * dkeep) + (tt & 7);
        uint4 hh[4];
        float2 st[4];
        uint32_t bs[4];
        const int slot = w - 8;
        int n = slot + NSLOT;
#pragma unroll 1
        for (int ph = 0; ph < 2; ph++) {
            epi1_help(sb, wg - 1, wq, lane, tm.u + dkeep * 22 * 512, 44 * (ft >> 2) + (wg == 2 ? 8 * (ft & 3) + 4 : 32 + 3 * (ft & 3)), ph);
            if (ph) {
                mbar_wait(sb + SM_BAR + 8 * B_S4, 0);
                fence_async();
#pragma unroll
                for (int k = 0; k < 4; k++) {
                    const int s2 = (tt >> 3) + 32 * k;
                    hh[k] = __ldcg(tm.hn + (dkeep * 32 + ((s2 >> 2) ^ ((ft >> 2) & 1))) * 512 + ((s2 & 3) * 16 + ft) * 8 + ((tt ^ ft) & 7));
                    st[k] = __ldcg(tm.st + (128 * ft + s2) * 4);
                    bs[k] = __ldg((const unsigned short*)b2 + 128 * ft + s2);
                }
                n += NSLOT;
            }
            if (slot < NSLOT) {
#pragma unroll 1
                for (; n < (ph ? 54 : 32); n += NSLOT) {
                    const uint4* src = item_src(tm.hn, tm.u, n, dkeep, r);
                    mbar_wait(sb + SM_BAR + 8 * (B_EMPTY + slot), (n / NSLOT - 1) & 1);
                    if (lane == 0) {
                        mbar_expect(sb + SM_BAR + 8 * (B_FULL + slot), 8192);
                        bulk_load(sb + SM_RING + slot * 8192, src, 8192, sb + SM_BAR + 8 * (B_FULL + slot));
                        if ((n | 1) == 31) mbar_arrive(sb + SM_BAR + 8 * B_TAIL);
                        TSX(32 + n);
                    }
                    __syncwarp();
                }
            }
        }
        float hf[32];
#pragma unroll
        for (int k = 0; k < 4; k++) {
            const uint32_t q[4] = {hh[k].x, hh[k].y, hh[k].z, hh[k].w};
            st[k].x += blo(bs[k]);
#pragma unroll
            for (int i = 0; i < 4; i++) { hf[8 * k + 2 * i] = fmaf(blo(q[i]), st[k].y, st[k].x); hf[8 * k + 2 * i + 1] = fmaf(bhi(q[i]), st[k].y, st[k].x); }
        }
        const uint32_t ya = sb + SM_W + 4 * 16384 + (tt >> 3) * 128 + (((tt ^ (tt >> 3)) & 7) * 16);
#pragma unroll 1
        for (int live = 0; live < 2; live++) {
            float hs[32];
            if (live) BAR_SYNC(10, 384);
#pragma unroll
            for (int k = 0; k < 4; k++) {
                const uint4 y = lds128(ya + 16384 + k * 4096);
                const uint32_t q[4] = {y.x, y.y, y.z, y.w};
#pragma unroll
                for (int i = 0; i < 4; i++) { hs[8 * k + 2 * i] = hf[8 * k + 2 * i] + blo(q[i]); hs[8 * k + 2 * i + 1] = hf[8 * k + 2 * i + 1] + bhi(q[i]); }
            }
            reg_fence(hs);
            if (live) BAR_SYNC(2, 384);
#pragma unroll
            for (int k = 0; k < 4; k++) {
                uint4 y = lds128(ya + k * 4096);
                stg128(live, op + k * 32 * 64, make_uint4(pack2(blo(y.x) + hs[8 * k], bhi(y.x) + hs[8 * k + 1]), pack2(blo(y.y) + hs[8 * k + 2], bhi(y.y) + hs[8 * k + 3]),
                                                          pack2(blo(y.z) + hs[8 * k + 4], bhi(y.z) + hs[8 * k + 5]), pack2(blo(y.w) + hs[8 * k + 6], bhi(y.w) + hs[8 * k + 7])));
            }
        }
        if (tid == 256) TSX(24);
    }
}

typedef CUresult (*EncodeFn)(CUtensorMap*, CUtensorMapDataType, cuuint32_t, void*, const cuuint64_t*, const cuuint64_t*, const cuuint32_t*,
                             const cuuint32_t*, CUtensorMapInterleave, CUtensorMapSwizzle, CUtensorMapL2promotion, CUtensorMapFloatOOBfill);

extern "C" void kernel_launch(void* const* d_in, const int* in_sizes, int n_in, void* d_out, int out_size) {
    static EncodeFn enc = nullptr;
    if (!enc) {
        void* fn = nullptr;
        cudaDriverEntryPointQueryResult qr;
        cudaGetDriverEntryPoint("cuTensorMapEncodeTiled", &fn, cudaEnableDefault, &qr);
        enc = (EncodeFn)fn;
        cudaFuncSetAttribute(fused_kernel, cudaFuncAttributeMaxDynamicSharedMemorySize, SM_TOTAL);
    }
    Maps tm;
    cudaGetSymbolAddress((void**)&tm.Y, g_Y); cudaGetSymbolAddress((void**)&tm.hn, g_hn); cudaGetSymbolAddress((void**)&tm.u, g_u);
    cudaGetSymbolAddress((void**)&tm.Y128, g_Y128); cudaGetSymbolAddress((void**)&tm.st, g_st); cudaGetSymbolAddress((void**)&tm.cnt, g_cnt);
    const cuuint32_t es[5] = {1, 1, 1, 1, 1};
    {
        const cuuint64_t P = 2752, R = 128 * P;
        for (int e = 0; e < 2; e++) {
            cuuint64_t dims[5] = {1376, 4, 2, 2, 128}, str[4] = {R, e ? 4 * R - 4 * P : 4 * R + 4 * P, 8 * R, P};
            cuuint32_t box[5] = {64, 4, 2, 2, 4};
            enc(&tm.m[e], CU_TENSOR_MAP_DATA_TYPE_BFLOAT16, 5, d_in[4], dims, str, box, es, CU_TENSOR_MAP_INTERLEAVE_NONE, CU_TENSOR_MAP_SWIZZLE_128B,
                CU_TENSOR_MAP_L2_PROMOTION_NONE, CU_TENSOR_MAP_FLOAT_OOB_FILL_NONE);
        }
        cuuint64_t dimt[4] = {1376, 2, 16, 124}, strt[3] = {4 * 2752, 128ull * 2752, 2752};
        cuuint32_t boxt[4] = {32, 2, 16, 4};
        enc(&tm.m[2], CU_TENSOR_MAP_DATA_TYPE_BFLOAT16, 4, d_in[4], dimt, strt, boxt, es, CU_TENSOR_MAP_INTERLEAVE_NONE, CU_TENSOR_MAP_SWIZZLE_64B,
            CU_TENSOR_MAP_L2_PROMOTION_NONE, CU_TENSOR_MAP_FLOAT_OOB_FILL_NONE);
    }
    {
        cuuint64_t dims[3] = {64, 1376, 32}, str[2] = {4096, 128};
        cuuint32_t box[3] = {64, 64, 2};
        enc(&tm.m[3], CU_TENSOR_MAP_DATA_TYPE_BFLOAT16, 3, d_in[6], dims, str, box, es, CU_TENSOR_MAP_INTERLEAVE_NONE, CU_TENSOR_MAP_SWIZZLE_128B,
            CU_TENSOR_MAP_L2_PROMOTION_NONE, CU_TENSOR_MAP_FLOAT_OOB_FILL_NONE);
    }
    for (int i = 0; i < 2; i++) {
        cuuint64_t dims[2] = {4112, 128}, str[1] = {8224};
        cuuint32_t box[2] = {32, 128};
        enc(&tm.m[4 + i], CU_TENSOR_MAP_DATA_TYPE_BFLOAT16, 2, d_in[1 + i], dims, str, box, es, CU_TENSOR_MAP_INTERLEAVE_NONE, CU_TENSOR_MAP_SWIZZLE_64B,
            CU_TENSOR_MAP_L2_PROMOTION_NONE, CU_TENSOR_MAP_FLOAT_OOB_FILL_NONE);
    }
    fused_kernel<<<NCTA, NTHR, SM_TOTAL, cudaStreamPerThread>>>((const __nv_bfloat16*)d_in[0], (const __nv_bfloat16*)d_in[4], (const __nv_bfloat16*)d_in[6],
                                                               (const __nv_bfloat16*)d_in[5], (const __nv_bfloat16*)d_in[7], (__nv_bfloat16*)d_out, tm);
}
```
